```python
import torch

def _softmax(x, axis=-1):
    return torch.softmax(x, dim=axis)
def _gelu(x):
    return torch.nn.functional.gelu(x, approximate="tanh")
def _silu(x):
    return torch.nn.functional.silu(x)
def _sigmoid(x):
    return torch.sigmoid(x)
def _layernorm(x, axis=-1, eps=1e-5):
    m = x.mean(dim=axis, keepdim=True)
    v = x.var(dim=axis, keepdim=True, unbiased=False)
    return (x - m) / torch.sqrt(v + eps)
def _scatter_add(tgt, idx, src, axis=0):
    return tgt.clone().index_add_(axis, idx, src)
def _segment_sum(src, seg, n):
    out = torch.zeros((n,) + src.shape[1:], dtype=src.dtype)
    return out.index_add_(0, seg, src)
def _pad(x, pw):
    flat = tuple(v for pair in reversed(pw) for v in pair)
    return torch.nn.functional.pad(x, flat)

kernel_name = 'standalone__deep_cross_pnn__recsys'

def setup_inputs():

    _w = (lambda a: (lambda t: t.to(torch.bfloat16) if t.is_floating_point() else t)(torch.as_tensor(a)))
    B, F, D, V = 16384, 100, 64, min(100000, 100000)
    H = 4 * D
    return {
        "idx": _w((lambda lo, hi, *s: torch.randint(lo, hi, s))(0, V, B, F).to(torch.int64)),
        "table": _w((lambda *s: torch.randn(*s, dtype=torch.bfloat16) * 1.6)(V, D) * (D ** -0.5)),
        "w_p": _w((lambda *s: torch.randn(*s, dtype=torch.bfloat16) * 0.05)(F * F) * ((F * F) ** -0.5)),
        "w1": _w((lambda *s: torch.randn(*s, dtype=torch.bfloat16) * 1.6)(F * D, H) * ((F * D) ** -0.5)),
        "b1": _w((lambda *s: torch.randn(*s, dtype=torch.bfloat16) * 12.8)(H) * 0.01),
        "w2": _w((lambda *s: torch.randn(*s, dtype=torch.bfloat16) * 0.05)(H) * (H ** -0.5)),
        "b2": _w((lambda *s: torch.randn(*s, dtype=torch.bfloat16) * 1.6)(1) * 0.01),
    }

def reference(idx, table, w_p, w1, b1, w2, b2):
    emb = table[idx]
    B = emb.shape[0]; F = emb.shape[1]; D = emb.shape[2]
    ip = torch.einsum('bid,bjd->bij', emb, emb)
    ip = ip.reshape(B, F * F)
    logit_p = ip @ w_p
    z = emb.reshape(B, F * D)
    h = _gelu(z @ w1 + b1)
    logit_d = h @ w2 + b2
    return logit_p + logit_d
```

```cpp
#include <cuda_runtime.h>
#include <cuda_bf16.h>
#include <cuda.h>
#include <stdint.h>
#include <type_traits>

namespace {

constexpr int BATCH = 16384;
constexpr int NF    = 100;
constexpr int HID   = 256;
constexpr int TM    = 128;
#define CLUSTER 4
#define STAGGER 1
#define EARLYM 1
#define EARLYP 0
#define PPROBE 0
#define PREL EARLYP
#define KFRONT 2
#define KFB 4
#define PG0 0
#define PG1 2
#define AG1 -1
#define AG2 0
#define UQ 1
#define UPRE 3
#define UPMIN 3
#define LDEP 0
#define UNI 0
#define IDX32 3
#define W2L 3
#define AGSEL 0
#define EMASK 7
#define PPOS2 3
#define PPOS0 0
#define WPRE 3
#define PCHK 0
#define PMID 2
#define PMIDM 0
#define MEARLY 0
#define XS 2
#define ELO 0
#define ELOM 3
#define ECH 2
#define WPROMO CU_TENSOR_MAP_L2_PROMOTION_L2_128B
#define EPL 0
#define BINIT 0
#define PO2 0
#define PQ0 4
#define UMC 1
#define UNIC 1
#define XPOLLS 4096
#define SPLIT 3
#define SPLIT0 3
constexpr int CSA   = CLUSTER;
constexpr int NS    = 3;

constexpr uint32_t W_BYTES = 32768, A_BYTES = 16384, P_BYTES = 12800, U_BYTES = 12288;
constexpr uint32_t OFF_W    = 0;
constexpr uint32_t OFF_A    = OFF_W + NS * W_BYTES;
constexpr uint32_t OFF_P    = OFF_A + NS * A_BYTES;
constexpr uint32_t OFF_U    = OFF_P + 4 * P_BYTES;
constexpr uint32_t OFF_BW   = OFF_U + U_BYTES;
constexpr uint32_t OFF_PART = OFF_BW + 1024;
constexpr uint32_t OFF_PR   = OFF_PART + 2048;
constexpr uint32_t OFF_WX   = OFF_PR + 8192;
constexpr uint32_t OFF_IA   = OFF_WX + 64;
constexpr uint32_t OFF_IR   = OFF_IA + 4096;
constexpr uint32_t OFF_IP   = OFF_IR + 2048;
constexpr uint32_t OFF_IQ   = OFF_IP + 2 * 832;
constexpr uint32_t OFF_END  = OFF_IQ + 2 * 400;
constexpr uint32_t OFF_BAR  = OFF_END;
constexpr uint32_t OFF_WP0  = OFF_P + P_BYTES, OFF_WP1 = OFF_P + 3 * P_BYTES, WP_CHUNKS = NF * NF * 2 / 16;
constexpr uint32_t BAR_FULLW  = OFF_BAR;
constexpr uint32_t BAR_EMPTYW = BAR_FULLW + 8 * NS;
constexpr uint32_t BAR_FULLA  = BAR_EMPTYW + 8 * NS;
constexpr uint32_t BAR_EMPTYA = BAR_FULLA + 16 * NS;
constexpr uint32_t BAR_FULLP  = BAR_EMPTYA + 16 * NS;
constexpr uint32_t BAR_EMPTYP = BAR_FULLP + 32;
constexpr uint32_t SMEM_USED  = BAR_EMPTYP + 32;
constexpr uint32_t BAR_U      = OFF_IP + 800;
constexpr uint32_t QD = 8, OFF_QI = 8 * P_BYTES;
constexpr uint32_t OFF_QS = OFF_QI + 4 * QD * 400;
constexpr uint32_t OFF_Q = 0, BAR_FULLQ = BAR_FULLW, BAR_EMPTYQ = BAR_FULLW + 64;
static_assert(OFF_QS + 4 * 512 <= OFF_WP0 && BAR_EMPTYQ + 64 <= BAR_FULLP, "layout of the PNN-only role");
constexpr int XA = 2 * KFRONT, XB = 2 * KFB;
__device__ unsigned long long g_xch[BATCH];
__device__ unsigned int g_cnt;
#define TR2(addr)
constexpr uint32_t SMEM_BYTES = SMEM_USED;
#define TR(addr)

constexpr bool ON_A = true;
constexpr bool ON_P = true;
#define EXPECT 0
#define UNLIKELY(x) (x)
__device__ __forceinline__ uint32_t smem_u32(const void* p) { return (uint32_t)__cvta_generic_to_shared(p); }

__device__ __forceinline__ void mbar_init(uint32_t bar, uint32_t cnt) {
  asm volatile("mbarrier.init.shared.b64 [%0], %1;" ::"r"(bar), "r"(cnt) : "memory");
}
__device__ __forceinline__ void mbar_wait(uint32_t bar, uint32_t parity) {
  uint32_t ok;
  asm volatile("{.reg .pred p; mbarrier.try_wait.parity.shared.b64 p, [%1], %2; selp.u32 %0,1,0,p;}"
               : "=r"(ok) : "r"(bar), "r"(parity) : "memory");
  if (UNLIKELY(!ok)) {
    int it = 0;
    do {
      asm volatile("{.reg .pred p; mbarrier.try_wait.parity.shared.b64 p, [%1], %2; selp.u32 %0,1,0,p;}"
                   : "=r"(ok) : "r"(bar), "r"(parity) : "memory");
      if (++it > (1 << 22)) break;
    } while (!ok);
  }
}
#define L2H ""
#define PA1 0
#define PA2 0
#define PA3 0
#define PP0 0
#define PP1 0
#define PP2 0
#define PACE (PA1 || PA2 || PA3 || PP0 || PP1 || PP2)
#define PFT 0
#define PFL 16
#define PFN PFL
#define WPL 1
#define WDYN 2
#define HINT 0
#define SPIN 0
template <int WHO>
__device__ __forceinline__ void mbar_wait_p(uint32_t bar, uint32_t parity) {
  if (SPIN & WHO) {
    uint32_t ok;
    int it = 0;
    do {
      asm volatile("{.reg .pred p; mbarrier.test_wait.parity.shared.b64 p, [%1], %2; selp.u32 %0,1,0,p;}"
                   : "=r"(ok) : "r"(bar), "r"(parity) : "memory");
      if (++it > (1 << 24)) break;
    } while (!ok);
    return;
  }
  mbar_wait(bar, parity);
}
__device__ __forceinline__ void mbar_wait2(uint32_t bar0, uint32_t bar1, uint32_t parity) {
  uint32_t ok;
  asm volatile("{.reg .pred p, q; mbarrier.try_wait.parity.shared.b64 p, [%1], %3; mbarrier.try_wait.parity.shared.b64 q, [%2], %3;\n"
               " and.pred p, p, q; selp.u32 %0,1,0,p;}"
               : "=r"(ok) : "r"(bar0), "r"(bar1), "r"(parity) : "memory");
  if (UNLIKELY(!ok)) {
    mbar_wait(bar0, parity);
    mbar_wait(bar1, parity);
  }
}
__device__ __forceinline__ void mbar_wait2_loop(uint32_t bar0, uint32_t bar1, uint32_t parity) {
  uint32_t ok;
  int it = 0;
  do {
    asm volatile("{.reg .pred p, q; mbarrier.try_wait.parity.shared.b64 p, [%1], %3; mbarrier.try_wait.parity.shared.b64 q, [%2], %3;\n"
                 " and.pred p, p, q; selp.u32 %0,1,0,p;}"
                 : "=r"(ok) : "r"(bar0), "r"(bar1), "r"(parity) : "memory");
    if (++it > (1 << 22)) break;
  } while (!ok);
}
__device__ __forceinline__ void mbar_wait_unless(bool ok, uint32_t bar, uint32_t parity) {
  asm volatile("{\n.reg .pred p, q;\n.reg .u32 it;\nsetp.ne.u32 p, %0, 0;\nmov.u32 it, 0;\n"
               "WAIT_LOOP:\n@!p mbarrier.try_wait.parity.shared.b64 p, [%1], %2;\nadd.u32 it, it, 1;\n"
               "setp.lt.and.u32 q, it, 4194304, !p;\n@q bra.uni WAIT_LOOP;\n}"
               ::"r"((uint32_t)ok), "r"(bar), "r"(parity) : "memory");
}
__device__ __forceinline__ void mbar_wait2_unless(bool ok, uint32_t bar0, uint32_t bar1, uint32_t parity) {
  asm volatile("{\n.reg .pred p, q, a, b;\n.reg .u32 it;\nsetp.ne.u32 p, %0, 0;\nmov.u32 it, 0;\n"
               "WAIT_LOOP:\n@!p mbarrier.try_wait.parity.shared.b64 a, [%1], %3;\n@!p mbarrier.try_wait.parity.shared.b64 b, [%2], %3;\n"
               "@!p and.pred p, a, b;\nadd.u32 it, it, 1;\n"
               "setp.lt.and.u32 q, it, 4194304, !p;\n@q bra.uni WAIT_LOOP;\n}"
               ::"r"((uint32_t)ok), "r"(bar0), "r"(bar1), "r"(parity) : "memory");
}
__device__ __forceinline__ void piece_end(uint32_t zero) {
  asm volatile("{\n.reg .pred q;\nPIECE_END:\nsetp.ne.u32 q, %0, 0;\n@q bra.uni PIECE_END;\n}" ::"r"(zero) : "memory");
}
__device__ __forceinline__ bool mbar_test(uint32_t bar, uint32_t parity) {
  uint32_t ok;
  asm volatile("{.reg .pred p; mbarrier.test_wait.parity.shared.b64 p, [%1], %2; selp.u32 %0,1,0,p;}"
               : "=r"(ok) : "r"(bar), "r"(parity) : "memory");
  return ok != 0;
}
__device__ __forceinline__ bool elect_one() {
  uint32_t p;
  asm volatile("{.reg .pred q; elect.sync _|q, 0xffffffff; selp.u32 %0,1,0,q;}" : "=r"(p));
  return p != 0;
}
__device__ __forceinline__ void lds128(uint32_t* r, uint32_t addr) {
  asm volatile("ld.shared.v4.b32 {%0,%1,%2,%3}, [%4];" : "=r"(r[0]), "=r"(r[1]), "=r"(r[2]), "=r"(r[3]) : "r"(addr) : "memory");
}
__device__ __forceinline__ void mbar_arrive_local(uint32_t bar) {
  asm volatile("mbarrier.arrive.shared.b64 _, [%0];" ::"r"(bar) : "memory");
}
__device__ __forceinline__ void mbar_arrive_cluster(uint32_t bar) {
  asm volatile("mbarrier.arrive.shared::cluster.b64 _, [%0];" ::"r"(bar) : "memory");
}
__device__ __forceinline__ uint32_t mapa(uint32_t addr, uint32_t rank) {
  uint32_t r;
  asm("mapa.shared::cluster.u32 %0, %1, %2;" : "=r"(r) : "r"(addr), "r"(rank));
  return r;
}
__device__ __forceinline__ void cp_async16(uint32_t dst, const void* src) {
  asm volatile("cp.async.cg.shared.global [%0], [%1], 16;" ::"r"(dst), "l"(src) : "memory");
}
template <int OFF, bool ON = true>
__device__ __forceinline__ void copy_pair(uint32_t e0, uint32_t e1, uint32_t c16, const uint32_t (&r)[4]) {
  if (!ON) { asm volatile("" ::"r"(r[0]), "r"(r[1]), "r"(r[2]), "r"(r[3])); return; }
  asm volatile("{\n.reg .b64 a, b;\n.reg .b32 x, y;\n"
               "add.u32 x, %3, %2;\nadd.u32 y, %5, %2;\nmov.b64 a, {x, %4};\nmov.b64 b, {y, %6};\n"
               "cp.async.cg.shared.global" L2H " [%0+%7], [a], 16;\ncp.async.cg.shared.global" L2H " [%1+%7], [b], 16;\n}"
               ::"r"(e0), "r"(e1), "r"(c16), "r"(r[0]), "r"(r[1]), "r"(r[2]), "r"(r[3]), "n"(OFF) : "memory");
}
template <int OFF, bool ON = true>
__device__ __forceinline__ void copy_one(uint32_t e0, uint32_t c16, uint32_t lo, uint32_t hi) {
  if (!ON) { asm volatile("" ::"r"(lo), "r"(hi)); return; }
  asm volatile("{\n.reg .b64 a;\n.reg .b32 x;\nadd.u32 x, %2, %1;\nmov.b64 a, {x, %3};\n"
               "cp.async.cg.shared.global" L2H " [%0+%4], [a], 16;\n}"
               ::"r"(e0), "r"(c16), "r"(lo), "r"(hi), "n"(OFF) : "memory");
}
template <int OFF, bool ON = true>
__device__ __forceinline__ void copy_quad(uint32_t e0, uint32_t e1, uint64_t tc, const uint32_t (&r)[4]) {
  if (!ON) { asm volatile("" ::"r"(r[0]), "r"(r[1]), "r"(r[2]), "r"(r[3])); return; }
  asm volatile("{\n.reg .b64 a, b, c, d;\n"
               "mad.wide.u32 a, %3, 128, %2;\nmad.wide.u32 b, %4, 128, %2;\nmad.wide.u32 c, %5, 128, %2;\nmad.wide.u32 d, %6, 128, %2;\n"
               "cp.async.cg.shared.global" L2H " [%0+%7], [a], 16;\ncp.async.cg.shared.global" L2H " [%1+%7], [b], 16;\n"
               "cp.async.cg.shared.global" L2H " [%0+%8], [c], 16;\ncp.async.cg.shared.global" L2H " [%1+%8], [d], 16;\n}"
               ::"r"(e0), "r"(e1), "l"(tc), "r"(r[0]), "r"(r[1]), "r"(r[2]), "r"(r[3]), "n"(OFF), "n"(OFF + 1024) : "memory");
}
template <int OFF, bool ON = true>
__device__ __forceinline__ void copy_single(uint32_t e0, uint64_t tc, uint32_t r) {
  if (!ON) { asm volatile("" ::"r"(r)); return; }
  asm volatile("{\n.reg .b64 a;\nmad.wide.u32 a, %2, 128, %1;\ncp.async.cg.shared.global" L2H " [%0+%3], [a], 16;\n}"
               ::"r"(e0), "l"(tc), "r"(r), "n"(OFF) : "memory");
}
__device__ __forceinline__ uint64_t row_address(uint64_t table, uint32_t row) {
  uint64_t a;
  asm("mad.wide.u32 %0, %1, 128, %2;" : "=l"(a) : "r"(row), "l"(table));
  return a;
}
__device__ __forceinline__ void cp_async_arrive(uint32_t bar) {
  asm volatile("cp.async.mbarrier.arrive.noinc.shared.b64 [%0];" ::"r"(bar) : "memory");
}
__device__ __forceinline__ void wg_fence()  { asm volatile("wgmma.fence.sync.aligned;" ::: "memory"); }
__device__ __forceinline__ void wg_commit() { asm volatile("wgmma.commit_group.sync.aligned;" ::: "memory"); }
template <int N> __device__ __forceinline__ void wg_wait() { asm volatile("wgmma.wait_group.sync.aligned %0;" ::"n"(N) : "memory"); }
template <int N> __device__ __forceinline__ void reg_fence(float (&d)[N]) {
#pragma unroll
  for (int i = 0; i < N; i++) asm volatile("" : "+f"(d[i])::"memory");
}
__device__ __forceinline__ void ldsm_x4_t(uint32_t (&r)[4], uint32_t addr) {
  asm volatile("ldmatrix.sync.aligned.m8n8.x4.trans.shared.b16 {%0,%1,%2,%3}, [%4];"
               : "=r"(r[0]), "=r"(r[1]), "=r"(r[2]), "=r"(r[3]) : "r"(addr) : "memory");
}
__device__ __forceinline__ void ldsm_x2_t(uint32_t& r0, uint32_t& r1, uint32_t addr) {
  asm volatile("ldmatrix.sync.aligned.m8n8.x2.trans.shared.b16 {%0,%1}, [%2];"
               : "=r"(r0), "=r"(r1) : "r"(addr) : "memory");
}
__device__ __forceinline__ float bf_lo(uint32_t x) { return __uint_as_float(x << 16); }
__device__ __forceinline__ float bf_hi(uint32_t x) { return __uint_as_float(x & 0xffff0000u); }
__device__ __forceinline__ float bf2f(unsigned short x) { return __uint_as_float((uint32_t)x << 16); }

__device__ __forceinline__ void mlp_mma(float (&d)[128], uint64_t da, uint64_t db) {
  asm volatile("wgmma.mma_async.sync.aligned.m64n256k16.f32.bf16.bf16 "
    "{%0, %1, %2, %3, %4, %5, %6, %7, %8, %9, %10, %11, %12, %13, %14, %15, "
    "%16, %17, %18, %19, %20, %21, %22, %23, %24, %25, %26, %27, %28, %29, %30, %31, "
    "%32, %33, %34, %35, %36, %37, %38, %39, %40, %41, %42, %43, %44, %45, %46, %47, "
    "%48, %49, %50, %51, %52, %53, %54, %55, %56, %57, %58, %59, %60, %61, %62, %63, "
    "%64, %65, %66, %67, %68, %69, %70, %71, %72, %73, %74, %75, %76, %77, %78, %79, "
    "%80, %81, %82, %83, %84, %85, %86, %87, %88, %89, %90, %91, %92, %93, %94, %95, "
    "%96, %97, %98, %99, %100, %101, %102, %103, %104, %105, %106, %107, %108, %109, %110, %111, "
    "%112, %113, %114, %115, %116, %117, %118, %119, %120, %121, %122, %123, %124, %125, %126, %127}, "
    "%128, %129, 1, 1, 1, 0, 1;\n"
    : "+f"(d[0]), "+f"(d[1]), "+f"(d[2]), "+f"(d[3]), "+f"(d[4]), "+f"(d[5]), "+f"(d[6]), "+f"(d[7]),
      "+f"(d[8]), "+f"(d[9]), "+f"(d[10]), "+f"(d[11]), "+f"(d[12]), "+f"(d[13]), "+f"(d[14]), "+f"(d[15]),
      "+f"(d[16]), "+f"(d[17]), "+f"(d[18]), "+f"(d[19]), "+f"(d[20]), "+f"(d[21]), "+f"(d[22]), "+f"(d[23]),
      "+f"(d[24]), "+f"(d[25]), "+f"(d[26]), "+f"(d[27]), "+f"(d[28]), "+f"(d[29]), "+f"(d[30]), "+f"(d[31]),
      "+f"(d[32]), "+f"(d[33]), "+f"(d[34]), "+f"(d[35]), "+f"(d[36]), "+f"(d[37]), "+f"(d[38]), "+f"(d[39]),
      "+f"(d[40]), "+f"(d[41]), "+f"(d[42]), "+f"(d[43]), "+f"(d[44]), "+f"(d[45]), "+f"(d[46]), "+f"(d[47]),
      "+f"(d[48]), "+f"(d[49]), "+f"(d[50]), "+f"(d[51]), "+f"(d[52]), "+f"(d[53]), "+f"(d[54]), "+f"(d[55]),
      "+f"(d[56]), "+f"(d[57]), "+f"(d[58]), "+f"(d[59]), "+f"(d[60]), "+f"(d[61]), "+f"(d[62]), "+f"(d[63]),
      "+f"(d[64]), "+f"(d[65]), "+f"(d[66]), "+f"(d[67]), "+f"(d[68]), "+f"(d[69]), "+f"(d[70]), "+f"(d[71]),
      "+f"(d[72]), "+f"(d[73]), "+f"(d[74]), "+f"(d[75]), "+f"(d[76]), "+f"(d[77]), "+f"(d[78]), "+f"(d[79]),
      "+f"(d[80]), "+f"(d[81]), "+f"(d[82]), "+f"(d[83]), "+f"(d[84]), "+f"(d[85]), "+f"(d[86]), "+f"(d[87]),
      "+f"(d[88]), "+f"(d[89]), "+f"(d[90]), "+f"(d[91]), "+f"(d[92]), "+f"(d[93]), "+f"(d[94]), "+f"(d[95]),
      "+f"(d[96]), "+f"(d[97]), "+f"(d[98]), "+f"(d[99]), "+f"(d[100]), "+f"(d[101]), "+f"(d[102]), "+f"(d[103]),
      "+f"(d[104]), "+f"(d[105]), "+f"(d[106]), "+f"(d[107]), "+f"(d[108]), "+f"(d[109]), "+f"(d[110]), "+f"(d[111]),
      "+f"(d[112]), "+f"(d[113]), "+f"(d[114]), "+f"(d[115]), "+f"(d[116]), "+f"(d[117]), "+f"(d[118]), "+f"(d[119]),
      "+f"(d[120]), "+f"(d[121]), "+f"(d[122]), "+f"(d[123]), "+f"(d[124]), "+f"(d[125]), "+f"(d[126]), "+f"(d[127])
    : "l"(da), "l"(db));
}
__device__ __forceinline__ void pnn_mma(float (&d)[52], const uint32_t (&a)[6][4], uint64_t du) {
  asm volatile("{\n.reg .b64 dd;\n"
    "add.s64 dd, %76, 0;\n"
    "wgmma.mma_async.sync.aligned.m64n104k16.f32.bf16.bf16 "
    "{%0, %1, %2, %3, %4, %5, %6, %7, %8, %9, %10, %11, %12, %13, %14, %15, "
    "%16, %17, %18, %19, %20, %21, %22, %23, %24, %25, %26, %27, %28, %29, %30, %31, "
    "%32, %33, %34, %35, %36, %37, %38, %39, %40, %41, %42, %43, %44, %45, %46, %47, "
    "%48, %49, %50, %51}, "
    "{%52, %53, %54, %55}, dd, 0, 1, 1, 0;\n"
    "add.s64 dd, %76, 208;\n"
    "wgmma.mma_async.sync.aligned.m64n88k16.f32.bf16.bf16 "
    "{%0, %1, %2, %3, %4, %5, %6, %7, %8, %9, %10, %11, %12, %13, %14, %15, "
    "%16, %17, %18, %19, %20, %21, %22, %23, %24, %25, %26, %27, %28, %29, %30, %31, "
    "%32, %33, %34, %35, %36, %37, %38, %39, %40, %41, %42, %43}, "
    "{%56, %57, %58, %59}, dd, 1, 1, 1, 0;\n"
    "add.s64 dd, %76, 384;\n"
    "wgmma.mma_async.sync.aligned.m64n72k16.f32.bf16.bf16 "
    "{%0, %1, %2, %3, %4, %5, %6, %7, %8, %9, %10, %11, %12, %13, %14, %15, "
    "%16, %17, %18, %19, %20, %21, %22, %23, %24, %25, %26, %27, %28, %29, %30, %31, "
    "%32, %33, %34, %35}, "
    "{%60, %61, %62, %63}, dd, 1, 1, 1, 0;\n"
    "add.s64 dd, %76, 528;\n"
    "wgmma.mma_async.sync.aligned.m64n56k16.f32.bf16.bf16 "
    "{%0, %1, %2, %3, %4, %5, %6, %7, %8, %9, %10, %11, %12, %13, %14, %15, "
    "%16, %17, %18, %19, %20, %21, %22, %23, %24, %25, %26, %27}, "
    "{%64, %65, %66, %67}, dd, 1, 1, 1, 0;\n"
    "add.s64 dd, %76, 640;\n"
    "wgmma.mma_async.sync.aligned.m64n40k16.f32.bf16.bf16 "
    "{%0, %1, %2, %3, %4, %5, %6, %7, %8, %9, %10, %11, %12, %13, %14, %15, "
    "%16, %17, %18, %19}, "
    "{%68, %69, %70, %71}, dd, 1, 1, 1, 0;\n"
    "add.s64 dd, %76, 720;\n"
    "wgmma.mma_async.sync.aligned.m64n24k16.f32.bf16.bf16 "
    "{%0, %1, %2, %3, %4, %5, %6, %7, %8, %9, %10, %11}, "
    "{%72, %73, %74, %75}, dd, 1, 1, 1, 0;\n"
    "}\n"
    : "=f"(d[0]), "=f"(d[1]), "=f"(d[2]), "=f"(d[3]), "=f"(d[4]), "=f"(d[5]), "=f"(d[6]), "=f"(d[7]),
      "=f"(d[8]), "=f"(d[9]), "=f"(d[10]), "=f"(d[11]), "=f"(d[12]), "=f"(d[13]), "=f"(d[14]), "=f"(d[15]),
      "=f"(d[16]), "=f"(d[17]), "=f"(d[18]), "=f"(d[19]), "=f"(d[20]), "=f"(d[21]), "=f"(d[22]), "=f"(d[23]),
      "=f"(d[24]), "=f"(d[25]), "=f"(d[26]), "=f"(d[27]), "=f"(d[28]), "=f"(d[29]), "=f"(d[30]), "=f"(d[31]),
      "=f"(d[32]), "=f"(d[33]), "=f"(d[34]), "=f"(d[35]), "=f"(d[36]), "=f"(d[37]), "=f"(d[38]), "=f"(d[39]),
      "=f"(d[40]), "=f"(d[41]), "=f"(d[42]), "=f"(d[43]), "=f"(d[44]), "=f"(d[45]), "=f"(d[46]), "=f"(d[47]),
      "=f"(d[48]), "=f"(d[49]), "=f"(d[50]), "=f"(d[51])
    : "r"(a[0][0]), "r"(a[0][1]), "r"(a[0][2]), "r"(a[0][3]), "r"(a[1][0]), "r"(a[1][1]), "r"(a[1][2]), "r"(a[1][3]),
      "r"(a[2][0]), "r"(a[2][1]), "r"(a[2][2]), "r"(a[2][3]), "r"(a[3][0]), "r"(a[3][1]), "r"(a[3][2]), "r"(a[3][3]),
      "r"(a[4][0]), "r"(a[4][1]), "r"(a[4][2]), "r"(a[4][3]), "r"(a[5][0]), "r"(a[5][1]), "r"(a[5][2]), "r"(a[5][3]), "l"(du));
}
__device__ __forceinline__ void pnn_mma_mid(float (&d)[52], const uint32_t (&a)[6][4], uint64_t du) {
  asm volatile("{\n.reg .b64 dd;\n"
    "add.s64 dd, %76, 0;\n"
    "wgmma.mma_async.sync.aligned.m64n104k16.f32.bf16.bf16 "
    "{%0, %1, %2, %3, %4, %5, %6, %7, %8, %9, %10, %11, %12, %13, %14, %15, "
    "%16, %17, %18, %19, %20, %21, %22, %23, %24, %25, %26, %27, %28, %29, %30, %31, "
    "%32, %33, %34, %35, %36, %37, %38, %39, %40, %41, %42, %43, %44, %45, %46, %47, "
    "%48, %49, %50, %51}, "
    "{%52, %53, %54, %55}, dd, 0, 1, 1, 0;\n"
    "add.s64 dd, %76, 208;\n"
    "wgmma.mma_async.sync.aligned.m64n88k16.f32.bf16.bf16 "
    "{%0, %1, %2, %3, %4, %5, %6, %7, %8, %9, %10, %11, %12, %13, %14, %15, "
    "%16, %17, %18, %19, %20, %21, %22, %23, %24, %25, %26, %27, %28, %29, %30, %31, "
    "%32, %33, %34, %35, %36, %37, %38, %39, %40, %41, %42, %43}, "
    "{%56, %57, %58, %59}, dd, 1, 1, 1, 0;\n"
    "wgmma.fence.sync.aligned;\n"
    "add.s64 dd, %76, 384;\n"
    "wgmma.mma_async.sync.aligned.m64n72k16.f32.bf16.bf16 "
    "{%0, %1, %2, %3, %4, %5, %6, %7, %8, %9, %10, %11, %12, %13, %14, %15, "
    "%16, %17, %18, %19, %20, %21, %22, %23, %24, %25, %26, %27, %28, %29, %30, %31, "
    "%32, %33, %34, %35}, "
    "{%60, %61, %62, %63}, dd, 1, 1, 1, 0;\n"
    "add.s64 dd, %76, 528;\n"
    "wgmma.mma_async.sync.aligned.m64n56k16.f32.bf16.bf16 "
    "{%0, %1, %2, %3, %4, %5, %6, %7, %8, %9, %10, %11, %12, %13, %14, %15, "
    "%16, %17, %18, %19, %20, %21, %22, %23, %24, %25, %26, %27}, "
    "{%64, %65, %66, %67}, dd, 1, 1, 1, 0;\n"
    "add.s64 dd, %76, 640;\n"
    "wgmma.mma_async.sync.aligned.m64n40k16.f32.bf16.bf16 "
    "{%0, %1, %2, %3, %4, %5, %6, %7, %8, %9, %10, %11, %12, %13, %14, %15, "
    "%16, %17, %18, %19}, "
    "{%68, %69, %70, %71}, dd, 1, 1, 1, 0;\n"
    "add.s64 dd, %76, 720;\n"
    "wgmma.mma_async.sync.aligned.m64n24k16.f32.bf16.bf16 "
    "{%0, %1, %2, %3, %4, %5, %6, %7, %8, %9, %10, %11}, "
    "{%72, %73, %74, %75}, dd, 1, 1, 1, 0;\n"
    "}\n"
    : "=f"(d[0]), "=f"(d[1]), "=f"(d[2]), "=f"(d[3]), "=f"(d[4]), "=f"(d[5]), "=f"(d[6]), "=f"(d[7]),
      "=f"(d[8]), "=f"(d[9]), "=f"(d[10]), "=f"(d[11]), "=f"(d[12]), "=f"(d[13]), "=f"(d[14]), "=f"(d[15]),
      "=f"(d[16]), "=f"(d[17]), "=f"(d[18]), "=f"(d[19]), "=f"(d[20]), "=f"(d[21]), "=f"(d[22]), "=f"(d[23]),
      "=f"(d[24]), "=f"(d[25]), "=f"(d[26]), "=f"(d[27]), "=f"(d[28]), "=f"(d[29]), "=f"(d[30]), "=f"(d[31]),
      "=f"(d[32]), "=f"(d[33]), "=f"(d[34]), "=f"(d[35]), "=f"(d[36]), "=f"(d[37]), "=f"(d[38]), "=f"(d[39]),
      "=f"(d[40]), "=f"(d[41]), "=f"(d[42]), "=f"(d[43]), "=f"(d[44]), "=f"(d[45]), "=f"(d[46]), "=f"(d[47]),
      "=f"(d[48]), "=f"(d[49]), "=f"(d[50]), "=f"(d[51])
    : "r"(a[0][0]), "r"(a[0][1]), "r"(a[0][2]), "r"(a[0][3]), "r"(a[1][0]), "r"(a[1][1]), "r"(a[1][2]), "r"(a[1][3]),
      "r"(a[2][0]), "r"(a[2][1]), "r"(a[2][2]), "r"(a[2][3]), "r"(a[3][0]), "r"(a[3][1]), "r"(a[3][2]), "r"(a[3][3]),
      "r"(a[4][0]), "r"(a[4][1]), "r"(a[4][2]), "r"(a[4][3]), "r"(a[5][0]), "r"(a[5][1]), "r"(a[5][2]), "r"(a[5][3]), "l"(du));
}

constexpr uint64_t DESC_A_HI = ((uint64_t)(1024 >> 4) << 32) | (1ull << 62) | (1ull << 16);
constexpr uint64_t DESC_W_HI = ((uint64_t)(1024 >> 4) << 32) | (1ull << 62) | ((uint64_t)(8192 >> 4) << 16);
constexpr uint64_t DESC_U_HI = ((uint64_t)(256 >> 4) << 32) | ((uint64_t)(128 >> 4) << 16);
__host__ __device__ constexpr uint32_t u_base(int s) { return 32u * (104 * s - 8 * s * (s - 1)); }

struct Consumer {
  uint32_t sb;
  uint32_t wg;
  uint32_t zero;
  uint32_t k16;
  uint32_t rel;
  uint32_t ldsm;
  uint32_t ldsmx;
};

template <int ST>
__device__ __forceinline__ bool mlp_probe(const Consumer& c, uint32_t ph) {
  const bool w = mbar_test(c.sb + BAR_FULLW + 8 * ST, ph), a = mbar_test(c.sb + BAR_FULLA + 8 * NS * c.wg + 8 * ST, ph);
  return w & a;
}
template <int ST>
__device__ __forceinline__ void mlp_wait(const Consumer& c, uint32_t ph) {
  mbar_wait2_loop(c.sb + BAR_FULLW + 8 * ST, c.sb + BAR_FULLA + 8 * NS * c.wg + 8 * ST, ph);
}
template <int ST, int PROBED = 0>
__device__ __forceinline__ void mlp_issue(const Consumer& c, float (&acc)[128], uint32_t ph, uint32_t tr = 0, bool ok = false) {
  if (PROBED == 2) {
  } else if (PROBED && EARLYM) {
    if (PCHK & 4) {
      mbar_wait2_unless(ok, c.sb + BAR_FULLW + 8 * ST, c.sb + BAR_FULLA + 8 * NS * c.wg + 8 * ST, ph);
    } else if (UNLIKELY(!ok)) {
      mbar_wait2_loop(c.sb + BAR_FULLW + 8 * ST, c.sb + BAR_FULLA + 8 * NS * c.wg + 8 * ST, ph);
    }
  } else {
    mbar_wait2_loop(c.sb + BAR_FULLW + 8 * ST, c.sb + BAR_FULLA + 8 * NS * c.wg + 8 * ST, ph);
  }
  const uint64_t da = DESC_A_HI | (uint64_t)(((c.sb & 0x3FFFFu) + OFF_A + ST * A_BYTES + c.wg * 8192) >> 4);
  const uint64_t db = DESC_W_HI | (uint64_t)(((c.sb & 0x3FFFFu) + OFF_W + ST * W_BYTES) >> 4);
  wg_fence();
#pragma unroll
  for (int kk = 0; kk < 4; kk++) {
    mlp_mma(acc, da + kk * 2, db + kk * 128);
  }
  wg_commit();
}
__device__ __forceinline__ void mlp_issue_rt(const Consumer& c, float (&acc)[128], uint32_t st, uint32_t ph) {
  mbar_wait2(c.sb + BAR_FULLW + 8 * st, c.sb + BAR_FULLA + 8 * NS * c.wg + 8 * st, ph);
  const uint64_t da = DESC_A_HI | (uint64_t)(((c.sb & 0x3FFFFu) + OFF_A + st * A_BYTES + c.wg * 8192) >> 4);
  const uint64_t db = DESC_W_HI | (uint64_t)(((c.sb & 0x3FFFFu) + OFF_W + st * W_BYTES) >> 4);
  wg_fence();
#pragma unroll
  for (int kk = 0; kk < 4; kk++) {
    mlp_mma(acc, da + kk * 2, db + kk * 128);
  }
  wg_commit();
}
template <int ST>
__device__ __forceinline__ void mlp_release(const Consumer& c) {
  if (c.rel) mbar_arrive_cluster(c.rel + 8 * ST);
}

template <int SLOT>
__device__ __forceinline__ void pnn_wait(const Consumer& c, uint32_t ph) { mbar_wait(c.sb + BAR_FULLP + 8 * (c.wg * 2 + SLOT), ph); }
template <int SLOT>
__device__ __forceinline__ bool pnn_probe(const Consumer& c, uint32_t ph) {
  return mbar_test(c.sb + BAR_FULLP + 8 * (c.wg * 2 + SLOT), ph);
}
template <int SLOT>
__device__ __forceinline__ void pnn_release(const Consumer& c) {
  __syncwarp();
  if (elect_one()) mbar_arrive_local(c.sb + BAR_EMPTYP + 8 * (c.wg * 2 + SLOT));
}
template <int SLOT>
__device__ __forceinline__ void pnn_load(const Consumer& c, uint32_t (&pa)[6][4], uint32_t (&px)[4]) {
#pragma unroll
  for (int s = 0; s < 6; s++) ldsm_x4_t(pa[s], c.ldsm + SLOT * P_BYTES + s * 2048);
}
template <int SLOT, bool MID = false>
__device__ __forceinline__ void pnn_issue(const Consumer& c, float (&pacc)[52], uint32_t (&pa)[6][4], uint32_t (&px)[4]) {
  const uint64_t du = DESC_U_HI | (uint64_t)(((c.sb & 0x3FFFFu) + OFF_U) >> 4);
  wg_fence();
  if (MID && (SLOT == 1 || (PMIDM & 1))) pnn_mma_mid(pacc, pa, du);
  else
  pnn_mma(pacc, pa, du);
  wg_commit();
  ldsm_x4_t(px, c.ldsmx + SLOT * P_BYTES);
  pnn_release<SLOT>(c);
}
__device__ __forceinline__ void pnn_extra_weights(const Consumer& c, uint32_t (&w)[4]) {
  lds128(w, c.sb + OFF_WX + ((c.ldsm >> 3) & 0x30));
}
__device__ __forceinline__ float pnn_extra(const uint32_t (&w)[4], const uint32_t (&px)[4]) {
  const float wa = __uint_as_float(w[0]), wb = __uint_as_float(w[1]), wc = __uint_as_float(w[2]), wd = __uint_as_float(w[3]);
  const float xa = bf_lo(px[0]), xb = bf_hi(px[0]), ya = bf_lo(px[1]), yb = bf_hi(px[1]);
  const float m2 = fmaf(bf_lo(px[2]), bf_hi(px[2]), bf_lo(px[3]) * bf_hi(px[3]));
  const float u = fmaf(xa, fmaf(wc, xb, wa * xa), wb * xb * xb);
  const float v = fmaf(ya, fmaf(wc, yb, wa * ya), wb * yb * yb);
  return fmaf(wd, m2, u + v);
}
__device__ __forceinline__ float pnn_extra(const Consumer& c, const uint32_t (&px)[4]) {
  uint32_t w[4];
  pnn_extra_weights(c, w);
  return pnn_extra(w, px);
}
template <int NEXT, int PARTS, int POS, class F>
__device__ __forceinline__ void pnn_epilogue(const Consumer& c, float (&pacc)[52], uint32_t (&pa)[6][4], uint32_t (&px)[4], float sx,
                                             uint32_t entry, bool okp, uint32_t ph, F probe) {
  if (POS == 0 || PARTS != 3) probe();
  reg_fence(pacc);
  float s0 = sx, s1 = 0.f, s2 = 0.f, s3 = 0.f;
  const uint32_t k16 = c.k16;
  auto mlo = [&](uint32_t x) {
    uint32_t r;
    asm volatile("mul.lo.u32 %0, %1, %2;" : "=r"(r) : "r"(x), "r"(k16));
    return __uint_as_float(r);
  };
  auto group = [&](int J) {
#pragma unroll
    for (int h = 0; h < 2; h++) {
      const int ng = 1 + 2 * (5 - J) + h;
      const uint32_t x = pa[J][2 * h], y = pa[J][2 * h + 1];
      constexpr int elo = (ELOM >> (1 - NEXT)) & 1 ? ELO : 0;
      const float xl = (elo & 1) ? mlo(x) : bf_lo(x), yl = elo ? mlo(y) : bf_lo(y);
      s0 = fmaf(xl, pacc[4 * ng + 0], s0);
      s1 = fmaf(bf_hi(x), pacc[4 * ng + 1], s1);
      if (ECH == 4) {
        s2 = fmaf(yl, pacc[4 * ng + 2], s2);
        s3 = fmaf(bf_hi(y), pacc[4 * ng + 3], s3);
      } else {
        s0 = fmaf(yl, pacc[4 * ng + 2], s0);
        s1 = fmaf(bf_hi(y), pacc[4 * ng + 3], s1);
      }
    }
  };
  auto pinned = [&](uint32_t a) {
    if (ECH == 4) return ((__float_as_uint(s0) | __float_as_uint(s1) | __float_as_uint(s2) | __float_as_uint(s3)) & c.zero) | a;
    return ((__float_as_uint(s0) | __float_as_uint(s1)) & c.zero) | a;
  };
  auto load = [&](int J, uint32_t a) { ldsm_x4_t(pa[J], a + NEXT * P_BYTES + J * 2048); };
  auto check = [&]() {
    if (PCHK & 1) mbar_wait_unless(okp, c.sb + BAR_FULLP + 8 * (c.wg * 2 + NEXT), ph);
    else if (UNLIKELY(!okp)) pnn_wait<NEXT>(c, ph);
  };
  auto piece = [&]() {
    if (PCHK & 2) piece_end(c.zero);
    else if (UNLIKELY(!okp)) pnn_wait<NEXT>(c, ph);
  };
  s0 = fmaf(bf_lo(px[0]), pacc[0], s0);
  s1 = fmaf(bf_hi(px[0]), pacc[1], s1);
  if (ECH == 4) {
    s2 = bf_lo(px[1]) * pacc[2];
    s3 = bf_hi(px[1]) * pacc[3];
  } else {
    s0 = fmaf(bf_lo(px[1]), pacc[2], s0);
    s1 = fmaf(bf_hi(px[1]), pacc[3], s1);
  }
  if (PARTS == 0) {
#pragma unroll
    for (int J = 0; J < 6; J++) {
      group(J);
      load(J, pinned(c.ldsm));
    }
  } else if (PARTS == 1) {
#pragma unroll
    for (int J = 0; J < 6; J++) group(J);
    asm volatile("" : "+f"(s0), "+f"(s1));
    check();
#pragma unroll
    for (int J = 0; J < 6; J++) load(J, c.ldsm);
  } else if (PARTS == 2) {
#pragma unroll
    for (int J = 0; J < 4; J++) group(J);
    asm volatile("" : "+f"(s0), "+f"(s1));
    check();
#pragma unroll
    for (int J = 0; J < 4; J++) load(J, c.ldsm);
    check();
    group(4);
    load(4, pinned(c.ldsm));
    group(5);
    load(5, pinned(c.ldsm));
  } else if (PARTS == 3) {
    group(0);
    group(1);
    if (ECH == 4) asm volatile("" : "+f"(s0), "+f"(s1), "+f"(s2), "+f"(s3));
    else asm volatile("" : "+f"(s0), "+f"(s1));
    check();
    if (POS == 1) probe();
    load(0, c.ldsm);
    load(1, c.ldsm);
    piece();
    if (POS == 2) probe();
    group(2);
    group(3);
    load(2, pinned(c.ldsm));
    load(3, pinned(c.ldsm));
    piece();
    if (POS == 3) probe();
    group(4);
    load(4, pinned(c.ldsm));
    if (POS == 4) probe();
    group(5);
    load(5, pinned(c.ldsm));
    if (POS == 5) probe();
  } else if (PARTS == 4) {
    group(0);
    group(1);
    group(2);
    asm volatile("" : "+f"(s0), "+f"(s1));
    check();
    load(0, c.ldsm);
    load(1, c.ldsm);
    load(2, c.ldsm);
    check();
    group(3);
    load(3, pinned(c.ldsm));
    group(4);
    load(4, pinned(c.ldsm));
    group(5);
    load(5, pinned(c.ldsm));
  }
  const uint32_t pr = c.sb + OFF_PR + c.wg * 4096 + entry * 512 + ((c.ldsm - (c.sb + OFF_P + c.wg * 2 * P_BYTES)) >> 2);
  asm volatile("st.shared.f32 [%0], %1;" ::"r"(pr), "f"(ECH == 4 ? (s0 + s1) + (s2 + s3) : s0 + s1) : "memory");
}

__device__ __forceinline__ float gelu2_tanh(float x) {
  const float u = x * fmaf(0.044715f * 0.7978845608028654f, x * x, 0.7978845608028654f);
  float t;
  asm("tanh.approx.f32 %0, %1;" : "=f"(t) : "f"(u));
  return fmaf(x, t, x);
}

struct Roles {
  int base;
  int npn;
  int n_mlp;
  int n_main;
  int nps;
  int nx;
  int n_b;
  int cs;
  uint32_t k16;
};
template <int CS, bool FULL>
__global__ void __launch_bounds__(384, 1)
deep_cross_pnn_kernel(const __grid_constant__ CUtensorMap tmw, const int* __restrict__ idx, const uint4* __restrict__ table,
                      const unsigned short* __restrict__ w_p, const uint32_t* __restrict__ b1, const uint32_t* __restrict__ w2,
                      const unsigned short* __restrict__ b2, __nv_bfloat16* __restrict__ out, const uint32_t zero,
                      const __grid_constant__ Roles ro) {
  extern __shared__ __align__(1024) uint8_t smem_raw[];
  const uint32_t sb = smem_u32(smem_raw);
  const int tid = threadIdx.x;
  const uint32_t lane = tid & 31;
  const uint32_t warp = __shfl_sync(0xffffffffu, tid >> 5, 0);
  const int cs = CS ? CS : ro.cs;
  const bool prime = CS ? FULL : ro.cs > 1;
  uint32_t rank = 0;
  if (CS != 1) asm volatile("mov.u32 %0, %%cluster_ctarank;" : "=r"(rank));
  const int npn = FULL || (CS == 0 && UNIC && XA == XB) ? 64 - XA : ro.npn;
  const int KF = (64 - npn) / 2;
  const bool only = !FULL && (int)blockIdx.x >= ro.n_mlp;
  const int m0 = FULL ? blockIdx.x * TM : ro.base + blockIdx.x * TM;
  auto sample = [&](int g, int r) { return m0 + g * 64 + r; };
  auto xsample = [&](int g, int s) {
    int q = min(((int)(blockIdx.x - ro.n_mlp) * 2 + g) * ro.nps + s, ro.nx - 1);
    const int qa = ro.n_main * 2 * XA;
    if (XA && q < qa) {
      const int cta = q / (XA ? 2 * XA : 1), r = q - cta * 2 * XA, w = r >= XA;
      return cta * TM + w * 64 + (64 - XA) + r - w * XA;
    }
    q -= qa;
    const int cta = q / (2 * XB), r = q - cta * 2 * XB, w = r >= XB;
    return (ro.n_main + cta) * TM + w * 64 + (64 - XB) + r - w * XB;
  };
  if (prime && LDEP == 0) asm volatile("griddepcontrol.launch_dependents;");
  auto prefetch_table = [&]() {
    constexpr uint32_t TB = 100000u * 128u;
    const uint32_t per = (TB / (gridDim.x * PFL) + 15) & ~15u, o = (blockIdx.x * PFL + lane) * per;
    if (FULL && lane < PFN && o < TB)
      asm volatile("cp.async.bulk.prefetch.L2.global [%0], %1;" ::"l"(reinterpret_cast<const char*>(table) + o), "r"(min(per, TB - o)) : "memory");
  };

  uint32_t b1v = 0;
  auto load_small = [&]() {
    const uint32_t ct = tid - 128;
#pragma unroll
    for (uint32_t k = 0; k < 5; k++) {
      const uint32_t ch = ct + 256 * k;
      if (ch < WP_CHUNKS) cp_async16(sb + (ch < 800 ? OFF_WP0 : OFF_WP1 - 12800) + ch * 16, reinterpret_cast<const char*>(w_p) + ch * 16);
    }
    if (ct < 128) {
      if (BINIT) asm volatile("ld.global.nc.u32 %0, [%1];" : "=r"(b1v) : "l"(b1 + ct));
      else asm volatile("cp.async.ca.shared.global [%0], [%1], 4;" ::"r"(sb + OFF_BW + ct * 8), "l"(b1 + ct) : "memory");
      asm volatile("cp.async.ca.shared.global [%0], [%1], 4;" ::"r"(sb + OFF_BW + ct * 8 + 4), "l"(w2 + ct) : "memory");
    }
  };
  if (warp >= 4) {
    if (!WPL) load_small();
  } else if (warp == 1 || warp == 2) {
    const uint32_t raw = sb + OFF_IR + (warp - 1) * 1024 + lane * 16;
    if (!only) {
      cp_async16(raw, idx + (size_t)sample(0, (warp - 1) * 32 + lane) * NF);
      cp_async16(raw + 512, idx + (size_t)sample(1, (warp - 1) * 32 + lane) * NF);
    }
    asm volatile("cp.async.commit_group;" ::: "memory");
  } else {
    const uint32_t g = warp == 0 ? 0 : 1;
    if (lane < 25 && !only) cp_async16(sb + OFF_IQ + g * 400 + lane * 16, reinterpret_cast<const char*>(idx + (size_t)sample(g, 0) * NF) + lane * 16);
    asm volatile("cp.async.commit_group;" ::: "memory");
    if (lane < 25 && !only) cp_async16(sb + OFF_IP + g * 832 + lane * 16, reinterpret_cast<const char*>(idx + (size_t)sample(g, 1) * NF) + lane * 16);
    asm volatile("cp.async.commit_group;" ::: "memory");
    if (lane < 7) asm volatile("prefetch.global.L2 [%0];" ::"l"(reinterpret_cast<const char*>(table) + (size_t)lane * (2u << 20)));
    if (PFT == 1 && warp == 3) prefetch_table();
  }
  if (tid == 0) {
    if (only) {
      for (int s = 0; s < 8; s++) {
        mbar_init(sb + BAR_FULLQ + 8 * s, 32);
        mbar_init(sb + BAR_EMPTYQ + 8 * s, 4);
      }
    } else
    for (int s = 0; s < NS; s++) {
      mbar_init(sb + BAR_FULLW + 8 * s, 1);
      mbar_init(sb + BAR_EMPTYW + 8 * s, 8 * cs);
      for (int g = 0; g < 2; g++) {
        mbar_init(sb + BAR_FULLA + 8 * (NS * g + s), 64);
        mbar_init(sb + BAR_EMPTYA + 8 * (NS * g + s), 4);
      }
    }
    for (int s = 0; s < 4; s++) {
      mbar_init(sb + BAR_FULLP + 8 * s, 32);
      mbar_init(sb + BAR_EMPTYP + 8 * s, 4);
    }
    mbar_init(sb + BAR_U, 8);
    asm volatile("fence.mbarrier_init.release.cluster;" ::: "memory");
    asm volatile("prefetch.tensormap [%0];" ::"l"((uint64_t)&tmw) : "memory");
  }
  __syncthreads();
  if (cs > 1) asm volatile("barrier.cluster.arrive.relaxed.aligned;" ::: "memory");
  if (prime && LDEP == 1) asm volatile("griddepcontrol.launch_dependents;");
  if (WPL && warp >= 4) load_small();
  if (PFT == 4 && warp == 3) prefetch_table();

  if (warp < 4) {
    asm volatile("setmaxnreg.dec.sync.aligned.u32 40;");
    const uint32_t r4 = lane >> 3, c8 = lane & 7;
    const uint32_t off0 = r4 * 128 + ((c8 ^ r4) << 4);
    const uint32_t c16 = c8 * 16;
    const uint64_t tb = (uint64_t)table;
    if ((warp == 1 || warp == 2) && !only) {
      const uint32_t h = warp - 1;
      const char* ip = reinterpret_cast<const char*>(idx + (size_t)sample(0, h * 32 + lane) * NF);
      constexpr int ip1 = 64 * NF * 4;
      const uint32_t raw = sb + OFF_IR + h * 1024 + lane * 16;
      const uint32_t sts = sb + OFF_IA + h * 2048 + 4 * ((lane & 16) | ((lane & 3) << 2) | ((lane >> 2) & 3));
      const uint64_t tc = tb + c16;
      const uint32_t lds = sb + OFF_IA + h * 2048 + r4 * 16;
      const uint64_t desc = (uint64_t)&tmw;
      const uint16_t wmask = (uint16_t)((1 << cs) - 1);
      auto issue_w = [&](uint32_t f, uint32_t wst) {
        if (elect_one()) {
          const uint32_t fb = sb + BAR_FULLW + 8 * wst;
          asm volatile("mbarrier.arrive.expect_tx.shared.b64 _, [%0], %1;" ::"r"(fb), "r"(W_BYTES) : "memory");
          const uint32_t dst = sb + OFF_W + wst * W_BYTES + rank * (W_BYTES / (CS ? CS : CSA));
          if (CS == 0 && UMC) {
            asm volatile("cp.async.bulk.tensor.3d.shared::cluster.global.mbarrier::complete_tx::bytes.multicast::cluster [%0], [%1, {%3, %4, %5}], [%2], %6;"
                         ::"r"(dst), "l"(desc), "r"(fb), "r"(0), "r"(f * 64), "r"(rank * (4 / CSA)), "h"(wmask) : "memory");
          } else if (cs == 1) {
            asm volatile("cp.async.bulk.tensor.3d.shared::cluster.global.mbarrier::complete_tx::bytes [%0], [%1, {%3, %4, %5}], [%2];"
                         ::"r"(dst), "l"(desc), "r"(fb), "r"(0), "r"(f * 64), "r"(0) : "memory");
          } else {
            asm volatile("cp.async.bulk.tensor.3d.shared::cluster.global.mbarrier::complete_tx::bytes.multicast::cluster [%0], [%1, {%3, %4, %5}], [%2], %6;"
                         ::"r"(dst), "l"(desc), "r"(fb), "r"(0), "r"(f * 64 + (CS == 8 ? (rank & 1) * 32 : 0)), "r"(CS == 8 ? rank >> 1 : rank * (4 / (CS ? CS : CSA))), "h"((uint16_t)((1 << (CS ? CS : CSA)) - 1)) : "memory");
          }
        }
        __syncwarp();
      };
      if (h == 0) {
        if (cs > 1) asm volatile("barrier.cluster.wait.aligned;" ::: "memory");
        issue_w(0, 0); issue_w(1, 1); issue_w(2, 2);
      }
      uint32_t st = 0, ph = 1, nred = 8 + 3 * KF;
#pragma unroll 1
      for (uint32_t f = 0; f < NF; f++) {
        if ((f & 3) == 0) {
          uint32_t n0[4], n1[4];
          asm volatile("cp.async.wait_group 0;" ::: "memory");
          lds128(n0, raw);
          lds128(n1, raw + 512);
          __syncwarp();
#pragma unroll
          for (int j = 0; j < 4; j++) {
            asm volatile("st.shared.b32 [%0], %1;" ::"r"(sts + j * 256), "r"(n0[j]) : "memory");
            asm volatile("st.shared.b32 [%0], %1;" ::"r"(sts + j * 256 + 128), "r"(n1[j]) : "memory");
          }
          __syncwarp();
          ip += 16;
          if (f + 4 < NF) {
            cp_async16(raw, ip);
            cp_async16(raw + 512, ip + ip1);
          }
          asm volatile("cp.async.commit_group;" ::: "memory");
        }
        const uint32_t l = lds + (f & 3) * (IDX32 & 1 ? 256 : 512);
        const uint32_t e0 = sb + OFF_A + st * A_BYTES + h * 4096 + off0, e1 = (e0 ^ 64) + 512;
        uint32_t r[8][4];
#pragma unroll
        for (int u = 0; u < 4; u++) lds128(r[u], l + u * 64);
        const uint32_t pha = ph;
        if (AG1 >= 0 && f == 1) mbar_wait(sb + BAR_FULLA + 8 * AG1, 0);
        if (AG2 >= 0 && AGSEL) {
          mbar_wait_p<1>(f == 2 ? sb + BAR_FULLA + 8 * AG2 : sb + BAR_EMPTYA + 8 * st, f == 2 ? 0 : pha);
        } else {
          if (AG2 >= 0 && f == 2) mbar_wait(sb + BAR_FULLA + 8 * AG2, 0);
          mbar_wait_p<1>(sb + BAR_EMPTYA + 8 * st, pha);
        }
        TR(ta_);
        copy_quad<0, ON_A>(e0, e1, tc, r[0]);
        copy_quad<2048, ON_A>(e0, e1, tc, r[1]);
        cp_async_arrive(sb + BAR_FULLA + 8 * st);
        mbar_wait_p<1>(sb + BAR_EMPTYA + 8 * (NS + st), pha);
        TR(ta_ + 4);
        bool wtodo = f >= NS && (f & 1) == h;
        if (WDYN != 3 && wtodo && mbar_test(sb + BAR_EMPTYW + 8 * st, ph)) {
          issue_w(f, st);
          wtodo = false;
        }
        TR(ta_ + 8);
        copy_quad<8192, ON_A>(e0, e1, tc, r[2]);
        if (wtodo && mbar_test(sb + BAR_EMPTYW + 8 * st, ph)) {
          issue_w(f, st);
          wtodo = false;
        }
        copy_quad<10240, ON_A>(e0, e1, tc, r[3]);
        cp_async_arrive(sb + BAR_FULLA + 8 * (NS + st));
        if (wtodo) {
          mbar_wait_p<2>(sb + BAR_EMPTYW + 8 * st, ph);
          issue_w(f, st);
        }
        TR(ta_ + 12);
        if (f == nred) {
          const uint32_t k = (f - 5 - 3 * KF) / 6;
          const uint32_t pr = sb + OFF_PR + h * 4096 + (k & 1) * 2048 + (lane >> 3) * 512 + (lane & 7) * 16;
          uint32_t v[4][4];
#pragma unroll
          for (int i = 0; i < 4; i++) lds128(v[i], pr + i * 128);
          float q[4];
#pragma unroll
          for (int i = 0; i < 4; i++)
            q[i] = (__uint_as_float(v[i][0]) + __uint_as_float(v[i][1])) + (__uint_as_float(v[i][2]) + __uint_as_float(v[i][3]));
          float t = (q[0] + q[1]) + (q[2] + q[3]);
          t += __shfl_xor_sync(0xffffffffu, t, 4);
          if ((lane & 4) == 0)
            asm volatile("st.shared.f32 [%0], %1;" ::"r"(sb + OFF_PART + (h * 64 + 4 * k + (lane >> 3)) * 16 + (lane & 3) * 4), "f"(t) : "memory");
          nred += 6;
          if (prime && (KFRONT & 1) && nred == 8 + 3 * KFRONT + 6 * ((64 - XA) / 4)) nred -= 3;
        }
        if (++st == NS) { st = 0; ph ^= 1; }
      }
      if (npn < 64) {
        uint32_t cnt;
        asm volatile("ld.relaxed.gpu.global.u32 %0, [%1];" : "=r"(cnt) : "l"(&g_cnt) : "memory");
        const uint32_t tag = cnt / ro.n_b + 1;
        const int nxr = 64 - npn, row = h * 64 + npn + (int)lane;
        bool have = (int)lane >= nxr;
        float v = 0.f;
#pragma unroll 1
        for (int it = 0; it < XPOLLS; it++) {
          if (!have) {
            unsigned long long e;
            asm volatile("ld.relaxed.gpu.global.b64 %0, [%1];" : "=l"(e) : "l"(g_xch + m0 + row) : "memory");
            if ((uint32_t)(e >> 32) == tag) { v = __uint_as_float((uint32_t)e); have = true; }
          }
          if (__all_sync(0xffffffffu, have)) break;
        }
        uint32_t miss = __ballot_sync(0xffffffffu, !have);
#pragma unroll 1
        while (miss) {
          const int l = __ffs(miss) - 1;
          miss &= miss - 1;
          const int* ix = idx + (size_t)(m0 + h * 64 + npn + l) * NF;
          const uint32_t* tab = reinterpret_cast<const uint32_t*>(table) + lane;
          float t = 0.f;
#pragma unroll 1
          for (int i = 0; i < NF; i++) {
            const uint32_t a = tab[(size_t)ix[i] * 32];
#pragma unroll 1
            for (int j = 0; j < NF; j++) {
              const uint32_t b = tab[(size_t)ix[j] * 32];
              t = fmaf(bf2f(w_p[i * NF + j]), fmaf(bf_lo(a), bf_lo(b), bf_hi(a) * bf_hi(b)), t);
            }
          }
#pragma unroll
          for (int o = 16; o; o >>= 1) t += __shfl_xor_sync(0xffffffffu, t, o);
          if ((int)lane == l) v = t;
        }
        if ((int)lane < nxr)
          asm volatile("st.shared.v4.f32 [%0], {%1, %2, %2, %2};" ::"r"(sb + OFF_PART + row * 16), "f"(v), "f"(0.f) : "memory");
      }
      __syncwarp();
      asm volatile("bar.arrive %0, 160;" ::"r"(2 + h) : "memory");
      if (cs > 1 && h != 0) asm volatile("barrier.cluster.wait.aligned;" ::: "memory");
    } else {
      const uint32_t g = warp < 2 ? 0 : 1;
      auto gather = [&](auto only_c) {
      constexpr bool ONLY = decltype(only_c)::value;
      constexpr uint32_t LG = ONLY ? 2 : 1;
      const int ns = ONLY ? ro.nps : npn, par = ONLY && (warp == 1 || warp == 2), inc = ONLY ? 2 : 1;
      const uint32_t gw = g * 2 + par;
      const char* isrc = reinterpret_cast<const char*>(idx + (size_t)(ONLY ? 0 : sample(g, 0)) * NF) + lane * 16;
      const uint32_t raw0 = sb + (ONLY ? OFF_QI + gw * QD * 400 : OFF_IQ + g * 400) + lane * 16;
      const uint32_t tab = sb + OFF_QS + gw * 512;
      auto idx_row = [&](int k) {
        uint32_t smp;
        asm volatile("ld.shared.u32 %0, [%1];" : "=r"(smp) : "r"(tab + k * 4) : "memory");
        return reinterpret_cast<const char*>(idx) + (size_t)smp * (NF * 4) + lane * 16;
      };
      if (ONLY) {
        for (int k = lane; k < 128; k += 32)
          asm volatile("st.shared.u32 [%0], %1;" ::"r"(tab + k * 4), "r"(xsample(g, par + 2 * k)) : "memory");
        __syncwarp();
#pragma unroll 1
        for (int k = 0; k < (int)QD; k++) {
          if (lane < 25) cp_async16(raw0 + k * 400, idx_row(k));
          asm volatile("cp.async.commit_group;" ::: "memory");
        }
      }
      const uint64_t tc = tb + c16;
      const uint32_t rawa = raw0 - lane * 16, rawb = sb + OFF_IP + g * 832;
      if (!ONLY) isrc += 800;
#pragma unroll 1
      for (int s = par; s < ns; s += inc) {
        const uint32_t slot = s & ((1 << LG) - 1);
        const uint32_t raw = ONLY ? rawa + ((s >> 1) & (QD - 1)) * 400 : slot ? rawb : rawa;
        asm volatile("cp.async.wait_group %0;" ::"n"(ONLY ? QD - 1 : 1) : "memory");
        __syncwarp();
        const uint32_t e0 = sb + (ONLY ? OFF_Q : OFF_P) + ((g << LG) + slot) * P_BYTES + off0, e1 = (e0 ^ 64) + 512;
        const uint32_t l = raw + r4 * 16;
        uint32_t r[6][4], tl;
#pragma unroll
        for (int u = 0; u < PQ0; u++) lds128(r[u], l + u * 64);
        if (PQ0 == 6) asm volatile("ld.shared.b32 %0, [%1];" : "=r"(tl) : "r"(raw + r4 * 4 + 384) : "memory");
        if (!ONLY && KF > 0 && PG0 >= 0 && s == 0) mbar_wait(sb + BAR_FULLA + 8 * (NS * g + PG0), 0);
        if (!ONLY && KF > 0 && PG1 >= 0 && s == 1) mbar_wait(sb + BAR_FULLA + 8 * (NS * g + PG1), 0);
        if (!ONLY && s == 1) mbar_wait(sb + BAR_U, 0);
        mbar_wait_p<4>(sb + (ONLY ? BAR_EMPTYQ : BAR_EMPTYP) + 8 * ((g << LG) + slot), ((s >> LG) & 1) ^ 1);
        copy_quad<0, ON_P>(e0, e1, tc, r[0]);
        copy_quad<2048, ON_P>(e0, e1, tc, r[1]);
        if (PQ0 < 6) {
#pragma unroll
          for (int u = PQ0; u < 6; u++) lds128(r[u], l + u * 64);
          asm volatile("ld.shared.b32 %0, [%1];" : "=r"(tl) : "r"(raw + r4 * 4 + 384) : "memory");
        }
        copy_quad<4096, ON_P>(e0, e1, tc, r[2]);
        copy_quad<6144, ON_P>(e0, e1, tc, r[3]);
        copy_quad<8192, ON_P>(e0, e1, tc, r[4]);
        copy_quad<10240, ON_P>(e0, e1, tc, r[5]);
        copy_single<12288, ON_P>(e0, tc, tl);
        cp_async_arrive(sb + (ONLY ? BAR_FULLQ : BAR_FULLP) + 8 * ((g << LG) + slot));
        __syncwarp();
        if (lane < 25) {
          if (ONLY) isrc = idx_row(min((s >> 1) + (int)QD, 127));
          if (s + (ONLY ? 2 * (int)QD : 2) < ns) cp_async16(raw + lane * 16, isrc);
          if (!ONLY) isrc += 400;
        }
        asm volatile("cp.async.commit_group;" ::: "memory");
      }
      };
      if (only) gather(std::true_type());
      else gather(std::false_type());
      if (cs > 1) asm volatile("barrier.cluster.wait.aligned;" ::: "memory");
    }
    if (cs > 1) {
      asm volatile("barrier.cluster.arrive.relaxed.aligned;" ::: "memory");
      asm volatile("barrier.cluster.wait.aligned;" ::: "memory");
    }
  } else {
    asm volatile("setmaxnreg.inc.sync.aligned.u32 232;");
    const int ct = tid - 128;
    Consumer c;
    c.sb = sb; c.wg = (warp - 4) >> 2;
    const uint32_t cw = warp & 3;
    c.zero = zero;
    c.k16 = ro.k16;
    if (cs > 1) asm volatile("barrier.cluster.wait.aligned;" ::: "memory");
    if (BINIT && tid < 256)
      asm volatile("st.shared.v4.b32 [%0], {%1, %2, %1, %2};" ::"r"(sb + OFF_PR + (tid - 128) * 16), "r"(b1v << 16), "r"(b1v & 0xffff0000u) : "memory");
    asm volatile("cp.async.wait_all;" ::: "memory");
    asm volatile("bar.sync 1, 256;" ::: "memory");
    TR2(sb + OFF_TR + 292);
    if (prime && LDEP == 2) asm volatile("griddepcontrol.launch_dependents;");
    auto wrow = [&](int i) { return sb + OFF_WP0 + i * (NF * 2) + (i >= 64 ? OFF_WP1 - OFF_WP0 - 12800 : 0); };
    auto lds16 = [](uint32_t a) { unsigned short v; asm volatile("ld.shared.u16 %0, [%1];" : "=h"(v) : "r"(a) : "memory"); return v; };
    auto u_build = [&](auto nu_c, int u0) {
      constexpr int NU = decltype(nu_c)::value;
      auto fld = [](int p) { return p < 96 ? (p & ~15) | ((p & 3) << 2) | ((p >> 2) & 3) : p; };
      auto lds32 = [](uint32_t a) { uint32_t v; asm volatile("ld.shared.u32 %0, [%1];" : "=r"(v) : "r"(a) : "memory"); return v; };
      uint32_t rw[NU][4];
      unsigned short cl[NU][8];
      int ii[NU], jj[NU];
#pragma unroll
      for (int u = 0; u < NU; u++) {
        const int ch = ct + 256 * (u0 + u);
        int s = 0;
#pragma unroll
        for (int k = 1; k < 6; k++) s += (ch >= (int)(u_base(k) / 16)) ? 1 : 0;
        const int q = ch - 2 * (104 * s - 8 * s * (s - 1));
        const int ng = q >> 4, kh = (q >> 3) & 1, r = q & 7;
        const int i = (ng == 0) ? 96 + r : 16 * (5 - ((ng - 1) >> 1)) + 8 * ((ng - 1) & 1) + r;
        const int j0 = 16 * s + 8 * kh;
        ii[u] = i; jj[u] = j0;
        const int fi = i < NF ? fld(i) : 0;
        const int f0 = 16 * s + 2 * kh;
        const uint32_t ra = wrow(fi) + f0 * 2, ca = wrow(f0) + fi * 2;
#pragma unroll
        for (int t = 0; t < 4; t++) {
          rw[u][t] = lds32(ra + 8 * t);
          cl[u][t] = lds16(ca + 4 * t * (NF * 2));
          cl[u][t + 4] = lds16(ca + (4 * t + 1) * (NF * 2));
        }
      }
#pragma unroll
      for (int u = 0; u < NU; u++) {
        float v[8];
#pragma unroll
        for (int t = 0; t < 8; t++) {
          const int j = jj[u] + t;
          const float a = (t < 4) ? bf_lo(rw[u][t]) : bf_hi(rw[u][t - 4]);
          const float x = j < ii[u] ? a + bf2f(cl[u][t]) : a;
          v[t] = (ii[u] < NF && j <= ii[u]) ? x : 0.f;
        }
        uint32_t pk[4];
#pragma unroll
        for (int e = 0; e < 4; e++) {
          const __nv_bfloat162 b = __floats2bfloat162_rn(v[2 * e], v[2 * e + 1]);
          pk[e] = *reinterpret_cast<const uint32_t*>(&b);
        }
        asm volatile("st.shared.v4.b32 [%0], {%1,%2,%3,%4};" ::"r"(sb + OFF_U + (ct + 256 * (u0 + u)) * 16), "r"(pk[0]), "r"(pk[1]), "r"(pk[2]), "r"(pk[3]) : "memory");
      }
    };
    auto u_small = [&]() {
      if (ct < 16) {
        const int i = 96 + ((0x10006E04u >> (2 * ct)) & 3), j = 96 + ((0x3020BED4u >> (2 * ct)) & 3);
        const float a = bf2f(lds16(wrow(i) + j * 2)), b = bf2f(lds16(wrow(j) + i * 2));
        const float v = ((0x44FFu >> ct) & 1) ? (i == j ? a : a + b) : 0.f;
        asm volatile("st.shared.f32 [%0], %1;" ::"r"(sb + OFF_WX + ct * 4), "f"(v) : "memory");
      }
    };
    if (only) {
      u_build(std::integral_constant<int, 3>(), 0);
      TR2(sb + OFF_TR + 296);
      u_small();
      asm volatile("fence.proxy.async.shared::cta;" ::: "memory");
      asm volatile("bar.sync 1, 256;" ::: "memory");
      TR2(sb + OFF_TR + 4);
    }
    {
      const uint32_t j = (lane & 7) + 8 * (lane >> 4);
      const uint32_t ch = 2 * cw + ((lane >> 3) & 1);
      c.ldsm = sb + OFF_P + c.wg * 2 * P_BYTES + j * 128 + ((ch ^ (lane & 7)) << 4);
      const uint32_t jx = 96 + (((lane & 16) ? 0x21302130u : 0x31203210u) >> (4 * (lane & 7)) & 3);
      c.ldsmx = sb + OFF_P + c.wg * 2 * P_BYTES + jx * 128 + ((ch ^ (jx & 7)) << 4);
    }
    if (only) {
      const uint32_t shift = (OFF_Q + c.wg * 4 * P_BYTES) - (OFF_P + c.wg * 2 * P_BYTES);
      const uint32_t lq = c.ldsm + shift, lx = c.ldsmx + shift;
      const uint32_t fq = sb + BAR_FULLQ + 32 * c.wg, eq = sb + BAR_EMPTYQ + 32 * c.wg;
      const uint32_t ring = sb + OFF_P + (c.wg * 4 + cw) * 1152, part = sb + OFF_P + 16384 + c.wg * 4096;
      const uint64_t du = DESC_U_HI | (uint64_t)(((sb & 0x3FFFFu) + OFF_U) >> 4);
      float pacc[52];
      uint32_t pa[6][4], pb[6][4], pxa[4], pxb[4], wx[4];
      pnn_extra_weights(c, wx);
      auto load = [&](uint32_t (&a)[6][4], uint32_t (&x)[4], int s) {
        const uint32_t slot = s & 3;
        mbar_wait(fq + 8 * slot, (s >> 2) & 1);
#pragma unroll
        for (int j = 0; j < 6; j++) ldsm_x4_t(a[j], lq + slot * P_BYTES + j * 2048);
        ldsm_x4_t(x, lx + slot * P_BYTES);
        __syncwarp();
        if (elect_one()) mbar_arrive_local(eq + 8 * slot);
      };
      auto reduce = [&](int blk) {
        uint32_t v[2][4];
        __syncwarp();
        lds128(v[0], ring + (lane & 7) * 144 + (lane >> 3) * 32);
        lds128(v[1], ring + (lane & 7) * 144 + (lane >> 3) * 32 + 16);
        float t = ((__uint_as_float(v[0][0]) + __uint_as_float(v[0][1])) + (__uint_as_float(v[0][2]) + __uint_as_float(v[0][3]))) +
                  ((__uint_as_float(v[1][0]) + __uint_as_float(v[1][1])) + (__uint_as_float(v[1][2]) + __uint_as_float(v[1][3])));
        t += __shfl_xor_sync(0xffffffffu, t, 8);
        t += __shfl_xor_sync(0xffffffffu, t, 16);
        if (lane < 8) asm volatile("st.shared.f32 [%0], %1;" ::"r"(part + (blk * 8 + lane) * 16 + cw * 4), "f"(t) : "memory");
      };
      auto step = [&](uint32_t (&a)[6][4], uint32_t (&x)[4], uint32_t (&b)[6][4], uint32_t (&y)[4], int s) {
        TR(tc_);
        wg_fence();
        pnn_mma(pacc, a, du);
        wg_commit();
        TR(tc_ + 4);
        if (s + 1 < ro.nps) load(b, y, s + 1);
        TR(tc_ + 8);
        float s0 = pnn_extra(wx, x), s1 = 0.f;
        TR(tc_ + 12);
        wg_wait<0>();
        reg_fence(pacc);
        TR(tc_ + 16);
        s0 = fmaf(bf_lo(x[0]), pacc[0], s0);
        s1 = fmaf(bf_hi(x[0]), pacc[1], s1);
        s0 = fmaf(bf_lo(x[1]), pacc[2], s0);
        s1 = fmaf(bf_hi(x[1]), pacc[3], s1);
        float s2 = 0.f, s3 = 0.f;
#pragma unroll
        for (int j = 0; j < 6; j++)
#pragma unroll
          for (int h = 0; h < 2; h++) {
            const int ng = 1 + 2 * (5 - j) + h;
            s0 = fmaf(bf_lo(a[j][2 * h]), pacc[4 * ng + 0], s0);
            s1 = fmaf(bf_hi(a[j][2 * h]), pacc[4 * ng + 1], s1);
            s2 = fmaf(bf_lo(a[j][2 * h + 1]), pacc[4 * ng + 2], s2);
            s3 = fmaf(bf_hi(a[j][2 * h + 1]), pacc[4 * ng + 3], s3);
          }
        asm volatile("st.shared.f32 [%0], %1;" ::"r"(ring + (s & 7) * 144 + lane * 4), "f"((s0 + s1) + (s2 + s3)) : "memory");
      };
      TR2(sb + OFF_TR + 32 + c.wg * 4);
      load(pa, pxa, 0);
#pragma unroll 1
      for (int s = 0; s < ro.nps; s += 2) {
        step(pa, pxa, pb, pxb, s);
        step(pb, pxb, pa, pxa, s + 1);
        if ((s & 6) == 6) reduce(s >> 3);
      }
      if (ro.nps & 7) reduce(ro.nps >> 3);
      TR2(sb + OFF_TR + 8 + c.wg * 4);
      asm volatile("bar.sync %0, 128;" ::"r"(2 + c.wg) : "memory");
      uint32_t cnt;
      asm volatile("ld.relaxed.gpu.global.u32 %0, [%1];" : "=r"(cnt) : "l"(&g_cnt) : "memory");
      const unsigned long long tag = (unsigned long long)(cnt / ro.n_b + 1) << 32;
      for (int s = ct & 127; s < ro.nps; s += 128) {
        uint32_t p4[4];
        lds128(p4, part + s * 16);
        const float v = (__uint_as_float(p4[0]) + __uint_as_float(p4[1])) + (__uint_as_float(p4[2]) + __uint_as_float(p4[3]));
        if (((int)(blockIdx.x - ro.n_mlp) * 2 + (int)c.wg) * ro.nps + s < ro.nx)
          asm volatile("st.relaxed.gpu.global.b64 [%0], %1;" ::"l"(g_xch + xsample(c.wg, s)), "l"(tag | __float_as_uint(v)) : "memory");
      }
      TR2(sb + OFF_TR + 16 + c.wg * 4);
    } else {
    c.rel = ((int)lane < cs) ? mapa(sb + BAR_EMPTYW, lane) : ((int)lane == cs) ? mapa(sb + BAR_EMPTYA + 8 * NS * c.wg, rank) : 0;

    float acc[128];
    float pacc[52];
    uint32_t pa[6][4], px[4];
#pragma unroll
    for (int nb = 0; nb < 32; nb++) {
      if (BINIT == 2) {
        asm volatile("ld.shared.v2.f32 {%0, %1}, [%2];" : "=f"(acc[4 * nb]), "=f"(acc[4 * nb + 1]) : "r"(sb + OFF_PR + (lane & 3) * 16 + nb * 64));
        asm volatile("ld.shared.v2.f32 {%0, %1}, [%2];" : "=f"(acc[4 * nb + 2]), "=f"(acc[4 * nb + 3]) : "r"(sb + OFF_PR + (lane & 3) * 16 + nb * 64 + 8));
        continue;
      }
      if (BINIT == 3) {
        asm volatile("ld.shared.v2.f32 {%0, %1}, [%2];" : "=f"(acc[4 * nb]), "=f"(acc[4 * nb + 1]) : "r"(sb + OFF_PR + (lane & 3) * 16 + nb * 64));
        acc[4 * nb + 2] = acc[4 * nb];
        acc[4 * nb + 3] = acc[4 * nb + 1];
        continue;
      }
      if (BINIT) {
        asm volatile("ld.shared.v4.f32 {%0, %1, %2, %3}, [%4];"
                     : "=f"(acc[4 * nb]), "=f"(acc[4 * nb + 1]), "=f"(acc[4 * nb + 2]), "=f"(acc[4 * nb + 3])
                     : "r"(sb + OFF_PR + (lane & 3) * 16 + nb * 64));
        continue;
      }
      uint32_t bb;
      asm volatile("ld.shared.b32 %0, [%1];" : "=r"(bb) : "r"(sb + OFF_BW + (lane & 3) * 8 + nb * 32));
      acc[4 * nb + 0] = acc[4 * nb + 2] = bf_lo(bb);
      acc[4 * nb + 1] = acc[4 * nb + 3] = bf_hi(bb);
    }

    TR2(sb + OFF_TR + 304);
    {
      int u = 0;
      auto u_piece = [&]() {
        u_build(std::integral_constant<int, 1>(), u);
        if (u == 0) u_small();
        if (++u == 3) {
          TR2(sb + OFF_TR + 296);
          asm volatile("fence.proxy.async.shared::cta;" ::: "memory");
          __syncwarp();
          if (lane == 0) mbar_arrive_local(sb + BAR_U);
          TR2(sb + OFF_TR + 4);
        }
      };
#pragma unroll 1
      while (u < UPRE) {
        if (u >= UPMIN && __all_sync(0xffffffffu, mbar_test(c.sb + BAR_FULLW, 0) & mbar_test(c.sb + BAR_FULLA + 8 * NS * c.wg, 0))) break;
        u_piece();
      }
      if (prime && LDEP == 3) asm volatile("griddepcontrol.launch_dependents;");
      mlp_issue<0>(c, acc, 0);
      TR2(sb + OFF_TR + 308);
      uint32_t st = 1, ph = 0;
#pragma unroll 1
      for (int f = 1; f <= 3 * KF; f++) {
        mlp_issue_rt(c, acc, st, ph);
        wg_wait<1>();
        const uint32_t prev = st == 0 ? 2 : st - 1;
        if (c.rel) mbar_arrive_cluster(c.rel + 8 * prev);
        if (++st == NS) { st = 0; ph ^= 1; }
        if (UPMIN < 3 && f >= UQ && u < 3) u_piece();
      }
      if (UPMIN < 3 && (!FULL || 3 * KFRONT < UQ + 2)) {
#pragma unroll 1
        while (u < 3) u_piece();
      }
      mbar_wait(sb + BAR_U, 0);
    }
    pnn_wait<0>(c, 0);
    TR2(sb + OFF_TR + 424 + c.wg * 16);
    pnn_load<0>(c, pa, px);
#pragma unroll 1
    for (int p = 0; p < npn / 2; p++) {
      const uint32_t php = p & 1, ph = (KFRONT & 1) && prime ? php ^ 1 : php;
      const uint32_t tb_ = 0;
      TR(tb_ + 0);
      TR2(sb + OFF_TR + (p * 2 + c.wg) * 4 + 32);
      pnn_issue<0, FULL>(c, pacc, pa, px);
      float sx = 0.f;
      uint32_t wx[4];
      if (XS & 1) {
        sx = pnn_extra(c, px);
        asm volatile("" : "+f"(sx));
      } else if (XS & 4) {
        pnn_extra_weights(c, wx);
      }
      bool okm = (EMASK & 1) && !(WPRE & 1) ? mlp_probe<1>(c, ph) : false;
      if (WPRE & 1) mlp_wait<1>(c, ph);
      if (MEARLY & 1) {
        mlp_issue<1, (WPRE & 1) ? 2 : (EMASK & 1)>(c, acc, ph, tb_ + 8, okm);
        wg_wait<2>();
        mlp_release<0>(c);
      } else {
        wg_wait<1>();
        TR(tb_ + 4);
        mlp_release<0>(c);
        mlp_issue<1, (WPRE & 1) ? 2 : (EMASK & 1)>(c, acc, ph, tb_ + 8, okm);
      }
      bool okp = SPLIT ? pnn_probe<1>(c, php) : true;
      if (!(XS & 1)) sx = (XS & 4) ? pnn_extra(wx, px) : pnn_extra(c, px);
      if (!SPLIT) pnn_wait<1>(c, php);
      TR(tb_ + 16);
      wg_wait<1>();
      TR(tb_ + 20);
      pnn_epilogue<1, SPLIT, PPOS2>(c, pacc, pa, px, sx, (2 * p) & 7, okp, php, [&]() { okm = (EMASK & 2) ? mlp_probe<2>(c, ph) : false; });

      TR(tb_ + 24);
      pnn_issue<1, FULL>(c, pacc, pa, px);
      if (XS & 8) {
        sx = pnn_extra(c, px);
        asm volatile("" : "+f"(sx));
      } else if (XS & 2) {
        pnn_extra_weights(c, wx);
      }
      if ((WPRE & 2) && (PCHK & 4)) mbar_wait2_unless(okm, c.sb + BAR_FULLW + 16, c.sb + BAR_FULLA + 8 * NS * c.wg + 16, ph);
      else if ((WPRE & 2) && UNLIKELY(!okm)) mlp_wait<2>(c, ph);
      if (MEARLY & 2) {
        mlp_issue<2, (WPRE & 2) ? 2 : (EMASK & 2) != 0>(c, acc, ph, tb_ + 32, okm);
        wg_wait<2>();
        mlp_release<1>(c);
      } else {
        wg_wait<1>();
        TR(tb_ + 28);
        mlp_release<1>(c);
        mlp_issue<2, (WPRE & 2) ? 2 : (EMASK & 2) != 0>(c, acc, ph, tb_ + 32, okm);
      }
      okp = SPLIT0 ? (pnn_probe<0>(c, php ^ 1) | (p == npn / 2 - 1)) : true;
      if (!(XS & 8)) sx = (XS & 2) ? pnn_extra(wx, px) : pnn_extra(c, px);
      if (!SPLIT0 && p < npn / 2 - 1) pnn_wait<0>(c, php ^ 1);
      TR(tb_ + 40);
      wg_wait<1>();
      TR(tb_ + 44);
      pnn_epilogue<0, SPLIT0, PPOS0>(c, pacc, pa, px, sx, (2 * p + 1) & 7, okp, php ^ 1, [&]() { okm = (EMASK & 4) ? mlp_probe<0>(c, ph ^ 1) : false; });

      TR(tb_ + 48);
      mlp_issue<0, (EMASK & 4) != 0>(c, acc, ph ^ 1, tb_ + 52, okm);
      wg_wait<1>();
      TR(tb_ + 60);
      mlp_release<2>(c);
    }
    TR2(sb + OFF_TR + 8 + c.wg * 4);
    unsigned short b2v;
    asm volatile("ld.global.nc.u16 %0, [%1];" : "=h"(b2v) : "l"(b2));
    if (c.wg == 1) {
      wg_wait<0>();
      mlp_release<0>(c);
      asm volatile("bar.sync 4, 256;" ::: "memory");
    }
    mlp_issue<1>(c, acc, 0);
    if (c.wg == 0) {
      wg_wait<1>();
      mlp_release<0>(c);
    }
    mlp_issue<2>(c, acc, 0);
    mlp_issue<0>(c, acc, 1);
    if (c.wg == 0) asm volatile("bar.arrive 4, 256;" ::: "memory");
    if (cs > 1) asm volatile("barrier.cluster.arrive.relaxed.aligned;" ::: "memory");
    asm volatile("bar.sync %0, 160;" ::"r"(2 + c.wg) : "memory");
    wg_wait<0>();
    reg_fence(acc);

    TR2(sb + OFF_TR + 16 + c.wg * 4);
    uint32_t tid2;
    asm volatile("mov.u32 %0, %%tid.x;" : "=r"(tid2));
    const uint32_t lane2 = tid2 & 31;
    float d0 = 0.f, d1 = 0.f;
    const uint32_t bw = sb + OFF_BW + 4 + (lane2 & 3) * 8;
#pragma unroll
    for (int nb = 0; nb < 32; nb++) {
      uint32_t ww;
      asm volatile("ld.shared.b32 %0, [%1];" : "=r"(ww) : "r"(bw + nb * 32));
      const float wl = bf_lo(ww), wh = bf_hi(ww);
      d0 = fmaf(gelu2_tanh(acc[4 * nb + 0]), wl, d0);
      d0 = fmaf(gelu2_tanh(acc[4 * nb + 1]), wh, d0);
      d1 = fmaf(gelu2_tanh(acc[4 * nb + 2]), wl, d1);
      d1 = fmaf(gelu2_tanh(acc[4 * nb + 3]), wh, d1);
    }
    d0 *= 0.5f;
    d1 *= 0.5f;
    d0 += __shfl_xor_sync(0xffffffffu, d0, 1);
    d1 += __shfl_xor_sync(0xffffffffu, d1, 1);
    d0 += __shfl_xor_sync(0xffffffffu, d0, 2);
    d1 += __shfl_xor_sync(0xffffffffu, d1, 2);
    if ((lane2 & 3) < 2) {
      const int r = ((tid2 - 128) >> 5) * 16 + (lane2 >> 2) + 8 * (lane2 & 1);
      uint32_t p4[4];
      lds128(p4, sb + OFF_PART + r * 16);
      const float pl = (__uint_as_float(p4[0]) + __uint_as_float(p4[1])) + (__uint_as_float(p4[2]) + __uint_as_float(p4[3]));
      const float v = ((lane2 & 1) ? d1 : d0) + bf2f(b2v) + pl;
      out[(FULL ? 0 : ro.base) + blockIdx.x * TM + r] = __float2bfloat16(v);
    }
    }
    if (!prime) {
      asm volatile("griddepcontrol.wait;" ::: "memory");
      if (tid == 128 && ro.n_main) atomicAdd(&g_cnt, 1u);
    }
    if (cs > 1) asm volatile("barrier.cluster.wait.aligned;" ::: "memory");
  }
}

typedef CUresult (*PFN_encodeTiled)(CUtensorMap*, CUtensorMapDataType, cuuint32_t, void*, const cuuint64_t*, const cuuint64_t*,
                                    const cuuint32_t*, const cuuint32_t*, CUtensorMapInterleave, CUtensorMapSwizzle,
                                    CUtensorMapL2promotion, CUtensorMapFloatOOBfill);

}

extern "C" void kernel_launch(void* const* d_in, const int* in_sizes, int n_in, void* d_out, int out_size) {
  (void)in_sizes; (void)n_in; (void)out_size;
  const int* idx = (const int*)d_in[0];
  const uint4* table = (const uint4*)d_in[1];
  const unsigned short* w_p = (const unsigned short*)d_in[2];
  void* w1 = d_in[3];
  const uint32_t* b1 = (const uint32_t*)d_in[4];
  const uint32_t* w2 = (const uint32_t*)d_in[5];
  const unsigned short* b2 = (const unsigned short*)d_in[6];

  static PFN_encodeTiled enc = nullptr;
  static Roles ro, ro_main;
  static int n_rest = 0;
  auto* const k_main = deep_cross_pnn_kernel<CSA, true>;
  auto* const k_rest = deep_cross_pnn_kernel<1, false>;
  auto* const k_plain = k_rest;
  auto config = [&](cudaLaunchConfig_t& cfg, cudaLaunchAttribute* at, int grid, int cs) {
    cfg = {};
    cfg.gridDim = dim3(grid);
    cfg.blockDim = dim3(384);
    cfg.dynamicSmemBytes = SMEM_BYTES;
    cfg.stream = cudaStreamPerThread;
    at[0].id = cudaLaunchAttributeClusterDimension;
    at[0].val.clusterDim.x = cs; at[0].val.clusterDim.y = 1; at[0].val.clusterDim.z = 1;
    cfg.attrs = at;
    cfg.numAttrs = 1;
  };
  cudaLaunchConfig_t cfg;
  cudaLaunchAttribute at[2];
  if (!enc) {
    void* fn = nullptr;
    cudaDriverEntryPointQueryResult qr;
    cudaGetDriverEntryPoint("cuTensorMapEncodeTiled", &fn, cudaEnableDefault, &qr);
    enc = (PFN_encodeTiled)fn;
    cudaFuncSetAttribute(k_main, cudaFuncAttributeMaxDynamicSharedMemorySize, SMEM_BYTES);
    cudaFuncSetAttribute(k_rest, cudaFuncAttributeMaxDynamicSharedMemorySize, SMEM_BYTES);
    cudaFuncSetAttribute(k_plain, cudaFuncAttributeMaxDynamicSharedMemorySize, SMEM_BYTES);
    int clusters = 0, sms = 0, dev = 0;
    config(cfg, at, BATCH / TM, CSA);
    cudaOccupancyMaxActiveClusters(&clusters, k_main, &cfg);
    cudaGetDevice(&dev);
    cudaDeviceGetAttribute(&sms, cudaDevAttrMultiProcessorCount, dev);
    int n_main = clusters * CSA < BATCH / TM ? clusters * CSA : BATCH / TM;
    const int n_mlp = BATCH / TM - n_main, n_only = sms - BATCH / TM;
    const int nx = 2 * (n_main * XA + n_mlp * XB);
    constexpr int NQ = PO2 ? 2 * PO2 : 2;
    const int nps = n_only > 0 ? ((nx + 2 * n_only - 1) / (2 * n_only) + NQ - 1) / NQ * NQ : 0;
    if (n_main > 0 && n_only > 0 && nps <= 248) {
      ro = {n_main * TM, 64 - XB, n_mlp, n_main, nps, nx, n_mlp + n_only, 1, 65536u};
      ro_main = {0, 64 - XA, n_main, n_main, nps, nx, n_mlp + n_only, CSA, 65536u};
      n_rest = n_mlp + n_only;
    } else {
      ro = {0, 64, BATCH / TM, 0, 0, 0, 1, 1, 65536u};
      n_rest = BATCH / TM;
    }
  }
  const int n_main = ro.n_main;
  auto w_map = [&](int cs) {
    CUtensorMap tmw;
    cuuint64_t gdim[3] = {64, (cuuint64_t)NF * 64, 4};
    cuuint64_t gstr[2] = {HID * 2, 128};
    cuuint32_t box[3] = {64, cs == 8 ? 32u : 64u, cs == 8 ? 1u : 4u / cs};
    cuuint32_t es[3] = {1, 1, 1};
    enc(&tmw, CU_TENSOR_MAP_DATA_TYPE_BFLOAT16, 3, w1, gdim, gstr, box, es, CU_TENSOR_MAP_INTERLEAVE_NONE,
        CU_TENSOR_MAP_SWIZZLE_128B, WPROMO, CU_TENSOR_MAP_FLOAT_OOB_FILL_NONE);
    return tmw;
  };
  if (n_main) {
    config(cfg, at, n_main, CSA);
    cudaLaunchKernelEx(&cfg, k_main, w_map(CSA), idx, table, w_p, b1, w2, b2, (__nv_bfloat16*)d_out, 0u, ro_main);
  }
  if (n_rest) {
    config(cfg, at, n_rest, 1);
    at[1].id = cudaLaunchAttributeProgrammaticStreamSerialization;
    at[1].val.programmaticStreamSerializationAllowed = 1;
    cfg.numAttrs = n_main ? 2 : 1;
    cudaLaunchKernelEx(&cfg, n_main ? k_rest : k_plain, w_map(1), idx, table, w_p, b1, w2, b2, (__nv_bfloat16*)d_out, 0u, ro);
  }
}
```
